```python
import torch

def _softmax(x, axis=-1):
    return torch.softmax(x, dim=axis)
def _gelu(x):
    return torch.nn.functional.gelu(x, approximate="tanh")
def _silu(x):
    return torch.nn.functional.silu(x)
def _sigmoid(x):
    return torch.sigmoid(x)
def _layernorm(x, axis=-1, eps=1e-5):
    m = x.mean(dim=axis, keepdim=True)
    v = x.var(dim=axis, keepdim=True, unbiased=False)
    return (x - m) / torch.sqrt(v + eps)
def _scatter_add(tgt, idx, src, axis=0):
    return tgt.clone().index_add_(axis, idx, src)
def _segment_sum(src, seg, n):
    out = torch.zeros((n,) + src.shape[1:], dtype=src.dtype)
    return out.index_add_(0, seg, src)
def _pad(x, pw):
    flat = tuple(v for pair in reversed(pw) for v in pair)
    return torch.nn.functional.pad(x, flat)

kernel_name = 'interleave_layers__linear_attn_block__grouped_kv_mqa__prompt'

def setup_inputs():

    _w = (lambda a: (lambda t: t.to(torch.bfloat16) if t.is_floating_point() else t)(torch.as_tensor(a)))
    def _A_setup():
        B, S, D = 1, 2048, 512
        return {
            "x": _w((lambda *s: torch.randn(*s, dtype=torch.bfloat16) * 0.05)(B, S, D)),
            "wqkv": _w((lambda *s: torch.randn(*s, dtype=torch.bfloat16) * 0.05)(D, 3 * D)),
            "wo": _w((lambda *s: torch.randn(*s, dtype=torch.bfloat16) * 0.05)(D, D)),
        }
    _A_in = _A_setup()

    def _B_setup():
        B, S, D, H = 1, 2048, 512, 32
        Dh = D // H
        return {
            "x": _w((lambda *s: torch.randn(*s, dtype=torch.bfloat16) * 0.05)(B, S, D)),
            "wq": _w((lambda *s: torch.randn(*s, dtype=torch.bfloat16) * 0.1)(D, H * Dh)),
            "wk": _w((lambda *s: torch.randn(*s, dtype=torch.bfloat16) * 0.1)(D, Dh)),
            "wv": _w((lambda *s: torch.randn(*s, dtype=torch.bfloat16) * 0.05)(D, Dh)),
            "wo": _w((lambda *s: torch.randn(*s, dtype=torch.bfloat16) * 0.05)(H * Dh, D)),
        }
    _B_in = _B_setup()

    return {
        "A_x": _A_in["x"],
        "A_wqkv": _A_in["wqkv"],
        "A_wo": _A_in["wo"],
        "B_x": _B_in["x"],
        "B_wq": _B_in["wq"],
        "B_wk": _B_in["wk"],
        "B_wv": _B_in["wv"],
        "B_wo": _B_in["wo"],
    }

def reference(A_x, A_wqkv, A_wo, B_x, B_wq, B_wk, B_wv, B_wo):
    def _A_ref(x, wqkv, wo):
        B, S, D = x.shape
        H = 32; Dh = D // H
        qkv = (lambda x, *d: x.permute(*d))((x @ wqkv).reshape(B, S, 3, H, Dh), 2, 0, 3, 1, 4)
        q, k, v = qkv[0], qkv[1], qkv[2]
        phi = lambda t: torch.where(t > 0, t + 1, torch.exp(t)) + 1e-6
        pq, pk = phi(q), phi(k)
        kv = torch.einsum("bhsd,bhse->bhde", pk, v)
        z = torch.einsum("bhsd->bhd", pk)
        num = torch.einsum("bhqd,bhde->bhqe", pq, kv)
        den = torch.einsum("bhqd,bhd->bhq", pq, z)[..., None] + 1e-6
        o = num / den
        return (lambda x, *d: x.permute(*d))(o, 0, 2, 1, 3).reshape(B, S, D) @ wo

    def _B_ref(x, wq, wk, wv, wo):
        B, S, D = x.shape
        H = 32
        Dh = D // H
        q = (lambda x, *d: x.permute(*d))((x @ wq).reshape(B, S, H, Dh), 0, 2, 1, 3)
        k = x @ wk
        v = x @ wv
        scores = torch.einsum("bhqd,bkd->bhqk", q, k) * (Dh ** -0.5)
        p = _softmax(scores, axis=-1)
        o = torch.einsum("bhqk,bkd->bhqd", p, v)
        return (lambda x, *d: x.permute(*d))(o, 0, 2, 1, 3).reshape(B, S, H * Dh) @ wo

    x = A_x
    x = x + _A_ref(_layernorm(x, axis=-1), A_wqkv, A_wo)
    x = x + _B_ref(_layernorm(x, axis=-1), B_wq, B_wk, B_wv, B_wo)
    x = x + _A_ref(_layernorm(x, axis=-1), A_wqkv, A_wo)
    x = x + _B_ref(_layernorm(x, axis=-1), B_wq, B_wk, B_wv, B_wo)
    return x
```

```cpp
#include <cuda_runtime.h>
#include <cuda.h>
#include <cuda_bf16.h>
#include <cuda_fp16.h>
#include <stdint.h>

#define DEVI __device__ __forceinline__

__device__ __align__(1024) uint4 g_ex[7][128][1088];
__device__ __align__(1024) uint4 g_part[2][4][32][32 * 18];
__device__ __align__(1024) uint4 g_fin[2][4][384];
__device__ __align__(1024) float g_cs[2080];
__device__ __align__(1024) uint8_t g_img[16 * 10240];
__device__ __align__(1024) __nv_bfloat16 g_kp[2048 * 16];
__device__ __align__(1024) float g_kmax[64];
__device__ __align__(1024) unsigned g_cnt[96];
#define PT(i)

constexpr uint32_t SM_XA = 0;
constexpr uint32_t SM_W = 65536;
constexpr uint32_t SM_IMG = 65536;
constexpr uint32_t SM_STG = 196608;
constexpr uint32_t SM_MISC = 229376;
constexpr uint32_t SM_ONES = SM_MISC;
constexpr uint32_t SM_KMAX = SM_MISC + 256;
constexpr uint32_t SM_STAT = SM_MISC + 512;
constexpr uint32_t SM_BAR = SM_MISC + 1024;
constexpr uint32_t SM_TOTAL = SM_MISC + 3072;
constexpr uint32_t SM_ZERO = SM_MISC + 2048;
constexpr int B_FULL = 0, B_EMPTY = 8, B_IMG = 16, B_TFREE = 32, B_X = 48, B_RDY = 104;
#define QD 2
#define GD0 500
#define GD1 500
#define GD2 500
#define KVD
#define KVT 0xFFFFF7F0u
constexpr int STAGE = 10240;
constexpr int MUMASK = 0x88;
constexpr uint32_t ORD_A = 0x76543210u, ORD_B = 0x75316420u;

DEVI uint32_t smem_u32(const void* p) { return (uint32_t)__cvta_generic_to_shared(p); }
DEVI void mbar_init(uint32_t a, uint32_t c) { asm volatile("mbarrier.init.shared::cta.b64 [%0], %1;" ::"r"(a), "r"(c)); }
DEVI void mbar_expect(uint32_t a, uint32_t b) { asm volatile("mbarrier.arrive.expect_tx.shared::cta.b64 _, [%0], %1;" ::"r"(a), "r"(b) : "memory"); }
DEVI void mbar_arrive(uint32_t a) { asm volatile("mbarrier.arrive.shared::cta.b64 _, [%0];" ::"r"(a) : "memory"); }
DEVI void mbar_arrive_n(uint32_t a, uint32_t n) { asm volatile("mbarrier.arrive.shared::cta.b64 _, [%0], %1;" ::"r"(a), "r"(n) : "memory"); }
DEVI void mbar_wait(uint32_t a, uint32_t ph) {
  asm volatile(
      "{\n.reg .pred p;\n.reg .u32 c;\nmov.u32 c,0;\nLW:\nmbarrier.try_wait.parity.shared::cta.b64 p, [%0], %1;\n@p bra DN;\n"
      "add.u32 c,c,1;\nsetp.lt.u32 p,c,2000000;\n@p bra LW;\ntrap;\nDN:\n}" ::"r"(a), "r"(ph) : "memory");
}
#define CHK(it) { if (it > 4000000) __trap(); }
DEVI void bulk_g2s(uint32_t dst, const void* src, uint32_t bytes, uint32_t bar) {
  asm volatile("cp.async.bulk.shared::cluster.global.mbarrier::complete_tx::bytes [%0], [%1], %2, [%3];" ::"r"(dst), "l"(src), "r"(bytes), "r"(bar) : "memory");
}
DEVI void tma3(uint32_t dst, const CUtensorMap* m, uint32_t bar, int c0, int c1, int c2) {
  asm volatile("cp.async.bulk.tensor.3d.shared::cluster.global.mbarrier::complete_tx::bytes [%0], [%1, {%3,%4,%5}], [%2];" ::"r"(dst), "l"(m), "r"(bar), "r"(c0), "r"(c1), "r"(c2) : "memory");
}
DEVI void tma4(uint32_t dst, const CUtensorMap* m, uint32_t bar, int c0, int c1, int c2, int c3) {
  asm volatile("cp.async.bulk.tensor.4d.shared::cluster.global.mbarrier::complete_tx::bytes [%0], [%1, {%3,%4,%5,%6}], [%2];" ::"r"(dst), "l"(m), "r"(bar), "r"(c0), "r"(c1), "r"(c2), "r"(c3) : "memory");
}
DEVI void l2_prefetch(const void* p, uint32_t bytes) { asm volatile("cp.async.bulk.prefetch.L2.global [%0], %1;" ::"l"(p), "r"(bytes) : "memory"); }
DEVI void bar_sync(int id, int n) { asm volatile("bar.sync %0, %1;" ::"r"(id), "r"(n) : "memory"); }
DEVI void bar_arrive(int id, int n) { asm volatile("bar.arrive %0, %1;" ::"r"(id), "r"(n) : "memory"); }
DEVI void fence_async() { asm volatile("fence.proxy.async;" ::: "memory"); }
DEVI void fence_async_smem() { asm volatile("fence.proxy.async.shared::cta;" ::: "memory"); }
DEVI void wg_fence() { asm volatile("wgmma.fence.sync.aligned;" ::: "memory"); }
DEVI void wg_commit() { asm volatile("wgmma.commit_group.sync.aligned;" ::: "memory"); }
template <int N> DEVI void wg_wait() { asm volatile("wgmma.wait_group.sync.aligned %0;" ::"n"(N) : "memory"); }
template <int N> DEVI void fence_regs(float* d) {
#pragma unroll
  for (int i = 0; i < N; i++) asm volatile("" : "+f"(d[i])::"memory");
}
DEVI void poll(const unsigned* c, unsigned target) {
  for (int it = 0;; it++) {
    unsigned v;
    asm volatile("ld.acquire.gpu.global.u32 %0, [%1];" : "=r"(v) : "l"(c) : "memory");
    if ((int)(v - target) >= 0) return;
    CHK(it);
  }
}
DEVI void poll_slow(const unsigned* c, unsigned target) {
#pragma unroll 1
  for (int i = 0; i < 4000000; i++) {
    unsigned v;
    asm volatile("ld.acquire.gpu.global.u32 %0, [%1];" : "=r"(v) : "l"(c) : "memory");
    if ((int)(v - target) >= 0) return;
    __nanosleep(300);
  }
  __trap();
}
DEVI uint4 ldcg128(const void* p) { uint4 v; asm volatile("ld.global.cg.v4.u32 {%0,%1,%2,%3}, [%4];" : "=r"(v.x), "=r"(v.y), "=r"(v.z), "=r"(v.w) : "l"(p) : "memory"); return v; }
DEVI uint2 ldcg64(const void* p) { uint2 v; asm volatile("ld.global.cg.v2.u32 {%0,%1}, [%2];" : "=r"(v.x), "=r"(v.y) : "l"(p) : "memory"); return v; }
DEVI uint32_t ldcg32(const void* p) { uint32_t v; asm volatile("ld.global.cg.u32 %0, [%1];" : "=r"(v) : "l"(p) : "memory"); return v; }
DEVI uint32_t ldcg16(const void* p) { uint16_t v; asm volatile("ld.global.cg.u16 %0, [%1];" : "=h"(v) : "l"(p) : "memory"); return v; }
DEVI void sts128(uint32_t a, uint4 v) { asm volatile("st.shared.v4.u32 [%0], {%1,%2,%3,%4};" ::"r"(a), "r"(v.x), "r"(v.y), "r"(v.z), "r"(v.w) : "memory"); }
DEVI void sts32(uint32_t a, uint32_t v) { asm volatile("st.shared.u32 [%0], %1;" ::"r"(a), "r"(v) : "memory"); }
DEVI void sts32f(uint32_t a, float v) { asm volatile("st.shared.f32 [%0], %1;" ::"r"(a), "f"(v) : "memory"); }
DEVI uint4 lds128(uint32_t a) { uint4 v; asm volatile("ld.shared.v4.u32 {%0,%1,%2,%3}, [%4];" : "=r"(v.x), "=r"(v.y), "=r"(v.z), "=r"(v.w) : "r"(a) : "memory"); return v; }
DEVI uint2 lds64(uint32_t a) { uint2 v; asm volatile("ld.shared.v2.u32 {%0,%1}, [%2];" : "=r"(v.x), "=r"(v.y) : "r"(a) : "memory"); return v; }
DEVI uint32_t lds32(uint32_t a) { uint32_t v; asm volatile("ld.shared.u32 %0, [%1];" : "=r"(v) : "r"(a) : "memory"); return v; }
DEVI float lds32f(uint32_t a) { float v; asm volatile("ld.shared.f32 %0, [%1];" : "=f"(v) : "r"(a) : "memory"); return v; }
DEVI void stsm4(uint32_t a, uint32_t r0, uint32_t r1, uint32_t r2, uint32_t r3) {
  asm volatile("stmatrix.sync.aligned.m8n8.x4.shared.b16 [%0], {%1,%2,%3,%4};" ::"r"(a), "r"(r0), "r"(r1), "r"(r2), "r"(r3) : "memory");
}
DEVI void stsm4t(uint32_t a, uint32_t r0, uint32_t r1, uint32_t r2, uint32_t r3) {
  asm volatile("stmatrix.sync.aligned.m8n8.x4.trans.shared.b16 [%0], {%1,%2,%3,%4};" ::"r"(a), "r"(r0), "r"(r1), "r"(r2), "r"(r3) : "memory");
}
DEVI uint32_t pack_bf(float lo, float hi) { uint32_t r; asm("cvt.rn.bf16x2.f32 %0, %1, %2;" : "=r"(r) : "f"(hi), "f"(lo)); return r; }
DEVI uint32_t pack_hf(float lo, float hi) { uint32_t r; asm("cvt.rn.f16x2.f32 %0, %1, %2;" : "=r"(r) : "f"(hi), "f"(lo)); return r; }
DEVI float bf_lo(uint32_t v) { return __uint_as_float(v << 16); }
DEVI float bf_hi(uint32_t v) { return __uint_as_float(v & 0xffff0000u); }
DEVI uint32_t add_bf2(uint32_t a, uint32_t b) { uint32_t r; asm("add.rn.bf16x2 %0, %1, %2;" : "=r"(r) : "r"(a), "r"(b)); return r; }
DEVI float ex2(float x) { float r; asm("ex2.approx.ftz.f32 %0, %1;" : "=f"(r) : "f"(x)); return r; }
DEVI float phi(float t) { return (ex2(fminf(t, 0.f) * 1.4426950408889634f) + 1e-6f) + fmaxf(t, 0.f); }

constexpr uint64_t D_SW128 = (1ull << 62) | ((uint64_t)(1024 >> 4) << 32) | (1ull << 16);
DEVI uint64_t desc_sw(uint32_t a) { return D_SW128 | (uint64_t)(a >> 4); }
DEVI uint64_t desc_ns(uint32_t a, uint32_t sbo, uint32_t lbo) { return ((uint64_t)(sbo >> 4) << 32) | ((uint64_t)(lbo >> 4) << 16) | (uint64_t)(a >> 4); }

#define R4(o) "+f"(d[o]), "+f"(d[o + 1]), "+f"(d[o + 2]), "+f"(d[o + 3])
template <int TA, int TB> DEVI void ss_n64(float* d, uint64_t a, uint64_t b) {
  asm volatile("wgmma.mma_async.sync.aligned.m64n64k16.f32.bf16.bf16 {%0,%1,%2,%3,%4,%5,%6,%7,%8,%9,%10,%11,%12,%13,%14,%15,%16,%17,%18,%19,%20,%21,%22,%23,%24,%25,%26,%27,%28,%29,%30,%31}, %32, %33, 1, 1, 1, %34, %35;"
               : R4(0), R4(4), R4(8), R4(12), R4(16), R4(20), R4(24), R4(28) : "l"(a), "l"(b), "n"(TA), "n"(TB));
}
template <int TA, int TB> DEVI void ss_n16(float* d, uint64_t a, uint64_t b) {
  asm volatile("wgmma.mma_async.sync.aligned.m64n16k16.f32.bf16.bf16 {%0,%1,%2,%3,%4,%5,%6,%7}, %8, %9, 1, 1, 1, %10, %11;"
               : R4(0), R4(4) : "l"(a), "l"(b), "n"(TA), "n"(TB));
}
template <int TA, int TB> DEVI void ss_n8(float* d, uint64_t a, uint64_t b) {
  asm volatile("wgmma.mma_async.sync.aligned.m64n8k16.f32.bf16.bf16 {%0,%1,%2,%3}, %4, %5, 1, 1, 1, %6, %7;"
               : R4(0) : "l"(a), "l"(b), "n"(TA), "n"(TB));
}
DEVI void qk_n64(float* d, float* e, const uint32_t* a, uint64_t desc) {
  asm volatile("wgmma.mma_async.sync.aligned.m64n64k16.f32.f16.f16 {%0,%1,%2,%3,%4,%5,%6,%7,%8,%9,%10,%11,%12,%13,%14,%15,%16,%17,%18,%19,%20,%21,%22,%23,%24,%25,%26,%27,%28,%29,%30,%31}, {%32,%33,%34,%35}, %36, 1, 1, 1, 0;"
               : R4(0), R4(4), R4(8), R4(12), "+f"(e[0]), "+f"(e[1]), "+f"(e[2]), "+f"(e[3]), "+f"(e[4]), "+f"(e[5]), "+f"(e[6]), "+f"(e[7]),
                 "+f"(e[8]), "+f"(e[9]), "+f"(e[10]), "+f"(e[11]), "+f"(e[12]), "+f"(e[13]), "+f"(e[14]), "+f"(e[15])
               : "r"(a[0]), "r"(a[1]), "r"(a[2]), "r"(a[3]), "l"(desc));
}
DEVI void pv_n24(float* d, const uint32_t* a, uint64_t desc) {
  asm volatile("wgmma.mma_async.sync.aligned.m64n24k16.f32.bf16.bf16 {%0,%1,%2,%3,%4,%5,%6,%7,%8,%9,%10,%11}, {%12,%13,%14,%15}, %16, 1, 1, 1, 1;"
               : R4(0), R4(4), R4(8) : "r"(a[0]), "r"(a[1]), "r"(a[2]), "r"(a[3]), "l"(desc));
}
DEVI void mma_bf(float* c, const uint32_t* a, uint32_t b0, uint32_t b1) {
  asm volatile("mma.sync.aligned.m16n8k16.row.col.f32.bf16.bf16.f32 {%0,%1,%2,%3}, {%4,%5,%6,%7}, {%8,%9}, {%0,%1,%2,%3};"
               : "+f"(c[0]), "+f"(c[1]), "+f"(c[2]), "+f"(c[3]) : "r"(a[0]), "r"(a[1]), "r"(a[2]), "r"(a[3]), "r"(b0), "r"(b1));
}

DEVI uint32_t exp_sw(float wa, float wb, int m1) {
  uint32_t R, u, E, P;
  asm("prmt.b32 %0,%1,%2,0x6521;" : "=r"(R) : "r"(__float_as_uint(wa)), "r"(__float_as_uint(wb)));
  asm("lop3.b32 %0,%1,0x007F007F,0x1F801F80,0xEA;" : "=r"(u) : "r"(R));
  asm("mad.lo.s32 %0,%1,%3,%2;" : "=r"(E) : "r"(u), "r"(R), "r"(m1));
  asm("fma.rn.bf16x2 %0,%1,%2,%3;" : "=r"(P) : "r"(R), "r"(u), "r"(E));
  return P;
}
DEVI uint32_t exp_mu(float wa, float wb) { return pack_bf(ex2(wa), ex2(wb)); }
template <int B0> DEVI void do_exp(float* S, uint32_t* P, int m1) {
#pragma unroll
  for (int i = 0; i < 16; i++) asm volatile("" : "+f"(S[i])::"memory");
#pragma unroll
  for (int b = 0; b < 4; b++) {
    if ((MUMASK >> ((B0 + b) & 7)) & 1) { P[2 * b] = exp_mu(S[4 * b], S[4 * b + 1]); P[2 * b + 1] = exp_mu(S[4 * b + 2], S[4 * b + 3]); }
    else { P[2 * b] = exp_sw(S[4 * b], S[4 * b + 1], m1); P[2 * b + 1] = exp_sw(S[4 * b + 2], S[4 * b + 3], m1); }
  }
#pragma unroll
  for (int i = 0; i < 8; i++) asm volatile("" : "+r"(P[i])::"memory");
}

DEVI void ln_stage(const __nv_bfloat16* x, uint32_t sb, int warp, int lane, int j) {
  uint4 v[4][2];
#pragma unroll
  for (int r = 0; r < 4; r++) {
    const __nv_bfloat16* p = x + (warp * 4 + r) * 512 + lane * 8;
    v[r][0] = ldcg128(p); v[r][1] = ldcg128(p + 256);
  }
  float m[4], q[4];
#pragma unroll
  for (int r = 0; r < 4; r++) {
    const uint32_t* u = (const uint32_t*)v[r];
    float s = 0.f;
#pragma unroll
    for (int i = 0; i < 8; i++) s += bf_lo(u[i]) + bf_hi(u[i]);
    m[r] = s;
    const int row = warp * 4 + r;
    if ((lane >> 4) == (j & 1)) sts128(sb + SM_STG + ((lane >> 3) & 1) * 8192 + row * 128 + (((lane & 7) ^ (row & 7)) << 4), j & 2 ? v[r][1] : v[r][0]);
  }
  __syncwarp();
  fence_regs<4>(m);
  PT(26);
#pragma unroll
  for (int o = 16; o; o >>= 1)
#pragma unroll
    for (int r = 0; r < 4; r++) m[r] += __shfl_xor_sync(~0u, m[r], o);
#pragma unroll
  for (int r = 0; r < 4; r++) {
    m[r] *= (1.f / 512.f);
    const uint32_t* u = (const uint32_t*)v[r];
    float s = 0.f;
#pragma unroll
    for (int i = 0; i < 8; i++) { float a = bf_lo(u[i]) - m[r], b = bf_hi(u[i]) - m[r]; s += a * a + b * b; }
    q[r] = s;
  }
#pragma unroll
  for (int o = 16; o; o >>= 1)
#pragma unroll
    for (int r = 0; r < 4; r++) q[r] += __shfl_xor_sync(~0u, q[r], o);
#pragma unroll
  for (int r = 0; r < 4; r++) {
    float rs = rsqrtf(q[r] * (1.f / 512.f) + 1e-5f), mb = -m[r] * rs;
    uint32_t* u = (uint32_t*)v[r];
#pragma unroll
    for (int i = 0; i < 8; i++) u[i] = pack_bf(fmaf(bf_lo(u[i]), rs, mb), fmaf(bf_hi(u[i]), rs, mb));
    int row = warp * 4 + r;
    uint32_t a = sb + SM_XA + (lane >> 3) * 8192 + row * 128 + (((lane & 7) ^ (row & 7)) << 4);
    sts128(a, v[r][0]); sts128(a + 4 * 8192, v[r][1]);
  }
}

DEVI uint4 ldr128(const void* p) { uint4 v; asm volatile("ld.relaxed.gpu.global.v4.u32 {%0,%1,%2,%3}, [%4];" : "=r"(v.x), "=r"(v.y), "=r"(v.z), "=r"(v.w) : "l"(p) : "memory"); return v; }
DEVI float2 ldr64f(const void* p) { float2 v; asm volatile("ld.relaxed.gpu.global.v2.f32 {%0,%1}, [%2];" : "=f"(v.x), "=f"(v.y) : "l"(p) : "memory"); return v; }
DEVI void str128(void* p, uint4 v) { asm volatile("st.relaxed.gpu.global.v4.u32 [%0], {%1,%2,%3,%4};" ::"l"(p), "r"(v.x), "r"(v.y), "r"(v.z), "r"(v.w) : "memory"); }
DEVI uint32_t nz(uint32_t w) { return max(w, 1u); }
DEVI uint32_t nzf(float w) { return max(__float_as_uint(w), 1u); }
DEVI bool pend(const uint4& v) { return min(min(v.x, v.y), min(v.z, v.w)) == 0; }
DEVI void ldsm4(uint32_t a, uint32_t* r) {
  asm volatile("ldmatrix.sync.aligned.m8n8.x4.shared.b16 {%0,%1,%2,%3}, [%4];" : "=r"(r[0]), "=r"(r[1]), "=r"(r[2]), "=r"(r[3]) : "r"(a) : "memory");
}
DEVI float rcp(float x) { float r; asm("rcp.approx.ftz.f32 %0, %1;" : "=f"(r) : "f"(x)); return r; }
DEVI uint32_t blk_addr(int rb, int lane) { return (16 * rb + (lane & 15)) * 128 + (((lane >> 4) ^ (lane & 7)) << 4); }

DEVI void gemm8(float* acc, uint32_t sb, uint32_t bars, uint32_t par, int blk, int lane, int j, uint32_t ord, uint32_t xb, uint32_t tab) {
#pragma unroll
  for (int i = 0; i < 32; i++) acc[i] = 0.f;
  const uint64_t a0 = desc_sw(sb + SM_XA);
  uint64_t b = desc_sw(sb + SM_W + blk * 8192);
  fence_regs<32>(acc);
#pragma unroll 1
  for (int s = 0; s < 8; s++) {
    const uint64_t a = a0 + ((2 * j + ord) & 7) * 512;
    if ((tab & 15) != 15) mbar_wait(xb + 8 * (tab & 15), 0);
    mbar_wait(bars + 8 * (B_FULL + s), par);
    wg_fence();
#pragma unroll
    for (int kk = 0; kk < 4; kk++) ss_n64<0, 1>(acc, a + kk * 2, b + kk * 128);
    wg_commit();
    b += 1024; ord >>= 4; tab >>= 4;
    wg_wait<1>();
    if (s > 0 && lane == 0) mbar_arrive_n(bars + 8 * (B_EMPTY + s - 1), 2);
  }
  wg_wait<0>();
  fence_regs<32>(acc);
  if (lane == 0) mbar_arrive_n(bars + 8 * (B_EMPTY + 7), 2);
}

DEVI void gather(int u, uint32_t sb, int g, int j, int gw, int lane, bool odd) {
  const int rb = gw & 3, hi = gw >> 2, cp = odd ? 1 : hi, cb0 = odd ? 2 * hi : 0;
  const uint4* src = &g_ex[u][4 * g][((cp * 4 + cb0) * 4 + rb) * 32 + lane];
  uint4 v[12];
  {
    const int c0 = clock(), d = (u & 1) ? GD1 : odd ? GD2 : GD0;
#pragma unroll 1
    while (clock() - c0 < d);
  }
#pragma unroll
  for (int s = 0; s < 3; s++)
#pragma unroll
    for (int i = 0; i < 4; i++) {
      if (i < 2 || !odd) v[4 * s + i] = ldr128(src + ((j + 1 + s) & 3) * 1088 + i * 128);
      else v[4 * s + i] = make_uint4(1, 1, 1, 1);
    }
  const uint32_t ad = (sb + SM_XA + cp * 8192 + blk_addr(rb, lane)) ^ (cb0 << 5);
#pragma unroll
  for (int s = 0; s < 3; s++) {
    const int jj = (j + 1 + s) & 3;
#pragma unroll 1
    for (int it = 0;; it++) {
      bool any = false;
#pragma unroll
      for (int i = 0; i < 4; i++)
        if (pend(v[4 * s + i])) { v[4 * s + i] = ldr128(src + jj * 1088 + i * 128); any = true; }
      if (!__any_sync(~0u, any)) break;
      CHK(it);
    }
#pragma unroll
    for (int i = 0; i < 4; i++)
      if (i < 2 || !odd) stsm4((ad + jj * 16384) ^ (i << 5), v[4 * s + i].x, v[4 * s + i].y, v[4 * s + i].z, v[4 * s + i].w);
    fence_async_smem();
    __syncwarp();
    if (lane == 0) mbar_arrive(sb + SM_BAR + 8 * (B_X + 8 * u + 1 + s));
  }
}

template <int NQ> DEVI void load_cs(float2* cs, const float* p) {
#pragma unroll 1
  for (int it = 0;; it++) {
    uint32_t m = ~0u;
#pragma unroll
    for (int i = 0; i < 2 * NQ; i++) { cs[i] = ldr64f(p + 8 * i); }
#pragma unroll
    for (int i = 0; i < 2 * NQ; i++) m = min(m, min(__float_as_uint(cs[i].x), __float_as_uint(cs[i].y)));
    if (__all_sync(~0u, m != 0)) break;
    CHK(it);
  }
}
template <int NQ> DEVI void ln_fold(float* acc, const float2* cs, uint32_t sb, int wq, int lane) {
  const uint2 a = lds64(sb + SM_STAT + (16 * wq + (lane >> 2)) * 8), b = lds64(sb + SM_STAT + (16 * wq + 8 + (lane >> 2)) * 8);
  const float r0 = __uint_as_float(a.x), m0 = __uint_as_float(a.y), r1 = __uint_as_float(b.x), m1 = __uint_as_float(b.y);
#pragma unroll
  for (int i = 0; i < 2 * NQ; i++) {
    acc[4 * i] = fmaf(acc[4 * i], r0, m0 * cs[i].x); acc[4 * i + 1] = fmaf(acc[4 * i + 1], r0, m0 * cs[i].y);
    acc[4 * i + 2] = fmaf(acc[4 * i + 2], r1, m1 * cs[i].x); acc[4 * i + 3] = fmaf(acc[4 * i + 3], r1, m1 * cs[i].y);
  }
}

__device__ __noinline__ void attn_fallback(uint32_t qa, float* O) {
  const int lane = threadIdx.x & 31, r = lane >> 2, c = lane & 3;
  uint32_t Q[4];
  ldsm4(qa, Q);
  float m0 = -INFINITY, m1 = -INFINITY;
  for (int kb = 0; kb < 2048; kb += 8) {
    float s[4] = {0.f, 0.f, 0.f, 0.f};
    const __nv_bfloat16* kp = g_kp + (kb + r) * 16 + 2 * c;
    mma_bf(s, Q, ldcg32(kp), ldcg32(kp + 8));
    m0 = fmaxf(m0, fmaxf(s[0], s[1])); m1 = fmaxf(m1, fmaxf(s[2], s[3]));
  }
  m0 = fmaxf(m0, __shfl_xor_sync(~0u, m0, 1)); m0 = fmaxf(m0, __shfl_xor_sync(~0u, m0, 2));
  m1 = fmaxf(m1, __shfl_xor_sync(~0u, m1, 1)); m1 = fmaxf(m1, __shfl_xor_sync(~0u, m1, 2));
  const float cs = 0.25f * 1.4426950408889634f;
  float o0[4] = {0.f, 0.f, 0.f, 0.f}, o1[4] = {0.f, 0.f, 0.f, 0.f}, d0 = 0.f, d1 = 0.f;
  for (int kb = 0; kb < 2048; kb += 16) {
    float s[4] = {0.f, 0.f, 0.f, 0.f}, t[4] = {0.f, 0.f, 0.f, 0.f};
    const __nv_bfloat16* kp = g_kp + (kb + r) * 16 + 2 * c;
    mma_bf(s, Q, ldcg32(kp), ldcg32(kp + 8));
    mma_bf(t, Q, ldcg32(kp + 128), ldcg32(kp + 136));
    uint32_t P[4];
    P[0] = pack_bf(ex2((s[0] - m0) * cs), ex2((s[1] - m0) * cs));
    P[1] = pack_bf(ex2((s[2] - m1) * cs), ex2((s[3] - m1) * cs));
    P[2] = pack_bf(ex2((t[0] - m0) * cs), ex2((t[1] - m0) * cs));
    P[3] = pack_bf(ex2((t[2] - m1) * cs), ex2((t[3] - m1) * cs));
    d0 += bf_lo(P[0]) + bf_hi(P[0]) + bf_lo(P[2]) + bf_hi(P[2]);
    d1 += bf_lo(P[1]) + bf_hi(P[1]) + bf_lo(P[3]) + bf_hi(P[3]);
    uint32_t vb[2][2];
    const int ch = kb >> 5;
    const uint32_t sg = ((MUMASK >> ((ch >> 3) & 7)) & 1) ? 0x80008000u : 0u;
#pragma unroll
    for (int hh = 0; hh < 2; hh++) {
      int st = (kb & 31) + 2 * c + 8 * hh;
      const uint8_t* vp = g_img + (st >> 1) * STAGE + 4096 + ch * 16 + r * 2;
#pragma unroll
      for (int ng = 0; ng < 2; ng++)
        vb[ng][hh] = (ldcg16(vp + ng * 2048) | (ldcg16(vp + ng * 2048 + 1024) << 16)) ^ sg;
    }
    mma_bf(o0, P, vb[0][0], vb[0][1]);
    mma_bf(o1, P, vb[1][0], vb[1][1]);
  }
  d0 += __shfl_xor_sync(~0u, d0, 1); d0 += __shfl_xor_sync(~0u, d0, 2);
  d1 += __shfl_xor_sync(~0u, d1, 1); d1 += __shfl_xor_sync(~0u, d1, 2);
  O[0] = o0[0]; O[1] = o0[1]; O[2] = o0[2]; O[3] = o0[3];
  O[4] = o1[0]; O[5] = o1[1]; O[6] = o1[2]; O[7] = o1[3];
  O[8] = d0; O[9] = d1;
}

DEVI void attn_pass(const int PASS, uint32_t sb, int lyr, const int m1) {
  const uint32_t bars = sb + SM_BAR;
  const int lane = threadIdx.x & 31;
  uint32_t Q[4];
  float n0, n1;
  {
    const int warp = threadIdx.x >> 5;
    uint32_t qv[4];
    ldsm4((sb + SM_XA + (2 * (blockIdx.x & 3) + PASS) * 8192 + blk_addr(warp & 3, lane)) ^ ((warp >> 2) << 5), qv);
    const float cs = 0.25f * 1.4426950408889634f;
#pragma unroll
    for (int i = 0; i < 4; i++) Q[i] = pack_hf(bf_lo(qv[i]) * cs, bf_hi(qv[i]) * cs);
    float2 a = __half22float2(*(__half2*)&Q[0]), b = __half22float2(*(__half2*)&Q[2]), c = __half22float2(*(__half2*)&Q[1]), d = __half22float2(*(__half2*)&Q[3]);
    n0 = a.x * a.x + a.y * a.y + b.x * b.x + b.y * b.y; n1 = c.x * c.x + c.y * c.y + d.x * d.x + d.y * d.y;
    n0 += __shfl_xor_sync(~0u, n0, 1); n0 += __shfl_xor_sync(~0u, n0, 2);
    n1 += __shfl_xor_sync(~0u, n1, 1); n1 += __shfl_xor_sync(~0u, n1, 2);
    n0 = sqrtf(n0) * 1.006f; n1 = sqrtf(n1) * 1.006f;
    mbar_wait(bars + 8 * B_IMG, lyr);
    const uint2 km = lds64(sb + SM_KMAX + lane * 8);
    const float kmax = __uint_as_float(__reduce_max_sync(~0u, max(km.x, km.y)));
    n0 = fmaf(n0, kmax, 0.25f); n1 = fmaf(n1, kmax, 0.25f);
  }
  bool bad = !(n0 <= 121.f && n1 <= 121.f);
  const float off0 = 242.f - n0, off1 = 242.f - n1;
  float Sa[16], Sb[16], O[12];
#pragma unroll
  for (int b = 0; b < 4; b++) {
    float i0, i1;
    if ((MUMASK >> b) & 1) { i0 = off0 - 191.f + 1.5860f; i1 = off1 - 191.f + 1.5860f; } else { i0 = off0 + 256.00390625f; i1 = off1 + 256.00390625f; }
    Sa[4 * b] = i0; Sa[4 * b + 1] = i0; Sa[4 * b + 2] = i1; Sa[4 * b + 3] = i1;
    if ((MUMASK >> (b + 4)) & 1) { i0 = off0 - 191.f + 1.5860f; i1 = off1 - 191.f + 1.5860f; } else { i0 = off0 + 256.00390625f; i1 = off1 + 256.00390625f; }
    Sb[4 * b] = i0; Sb[4 * b + 1] = i0; Sb[4 * b + 2] = i1; Sb[4 * b + 3] = i1;
  }
#pragma unroll
  for (int i = 0; i < 12; i++) O[i] = 0.f;
  uint32_t P0[8], P1[8];
  const uint64_t dK = desc_ns(sb + SM_IMG, 128, 2048), dV = desc_ns(sb + SM_IMG + 4096, 2048, 128);
  fence_regs<16>(Sa); fence_regs<16>(Sb); fence_regs<12>(O);
  wg_fence(); qk_n64(Sa, Sb, Q, dK); wg_commit();
  uint64_t v = dV, k = dK + 64;
  const bool fr = PASS == 1 && lane == 0;
  wg_wait<0>();
#pragma unroll 1
  for (int t = 0; t < 16; t++) {
    do_exp<0>(Sa, P0, m1);
    wg_fence(); pv_n24(O, P0, v); v += 16; pv_n24(O, P0 + 4, v); v += 16;
    do_exp<4>(Sb, P1, m1);
    wg_fence(); pv_n24(O, P1, v); v += 16; pv_n24(O, P1 + 4, v); v += 16; qk_n64(Sa, Sb, Q, k); k += 640 - 64; wg_commit();
    wg_wait<0>();
    if (fr && t > 0) mbar_arrive(bars + 8 * (B_TFREE + t - 1));
    do_exp<0>(Sa, P0, m1);
    wg_fence(); pv_n24(O, P0, v); v += 16; pv_n24(O, P0 + 4, v); v += 16;
    do_exp<4>(Sb, P1, m1);
    if (PASS == 0) mbar_wait(bars + 8 * (B_IMG + ((t + 1) & 15)), lyr);
    wg_fence(); pv_n24(O, P1, v); v += 16; pv_n24(O, P1 + 4, v); v += 640 - 112; qk_n64(Sa, Sb, Q, k); k += 64; wg_commit();
    wg_wait<0>();
  }
  fence_regs<12>(O); fence_regs<16>(Sa); fence_regs<16>(Sb);
  float d0 = __shfl_sync(~0u, O[8], lane & ~3), d1 = __shfl_sync(~0u, O[10], lane & ~3);
  bad |= !(d0 < -1e-21f && d0 > -3.6e19f && d1 < -1e-21f && d1 > -3.6e19f);
  int tid, bid;
  asm volatile("mov.u32 %0, %%tid.x;" : "=r"(tid)); asm volatile("mov.u32 %0, %%ctaid.x;" : "=r"(bid));
  const uint32_t oa = (sb + SM_XA + (2 * (bid & 3) + PASS) * 8192 + blk_addr((tid >> 5) & 3, tid & 31)) ^ ((tid >> 7) << 5);
  if (__any_sync(~0u, bad)) {
    float F[10];
    attn_fallback(oa, F);
#pragma unroll
    for (int i = 0; i < 8; i++) O[i] = F[i];
    d0 = F[8]; d1 = F[9];
  }
  const float i0 = 1.f / d0, i1 = 1.f / d1;
  const uint4 o = make_uint4(nz(pack_bf(O[0] * i0, O[1] * i0)), nz(pack_bf(O[2] * i1, O[3] * i1)), nz(pack_bf(O[4] * i0, O[5] * i0)), nz(pack_bf(O[6] * i1, O[7] * i1)));
  mbar_wait(bars + 8 * B_RDY, 1);
  str128(&g_ex[4 * lyr + 2][bid][PASS * 512 + tid], o);
  stsm4(oa, o.x, o.y, o.z, o.w);
  fence_async_smem();
  __syncwarp();
  if ((tid & 31) == 0) mbar_arrive(bars + 8 * (B_X + 8 * (4 * lyr + 2) + (PASS ? 0 : 4)));
}

DEVI void reset_piece(int l, uint32_t sb, int bid, int k) {
  const int i = k - 9, u = (i * 241) >> 12;
  uint4* q = k < 9 ? &g_part[l][bid & 3][bid >> 2][k * 64] : &g_ex[2 * l + u][bid][(i - 17 * u) * 64];
  asm volatile("cp.async.bulk.global.shared::cta.bulk_group [%0], [%1], 1024;" ::"l"(q), "r"(sb + SM_ZERO) : "memory");
}
DEVI void reset_wait() {
  asm volatile("cp.async.bulk.commit_group;" ::: "memory");
  asm volatile("cp.async.bulk.wait_group 0;" ::: "memory");
  fence_async();
  __threadfence();
}

struct Params {
  CUtensorMap tmKV, tmQ, tmWoA, tmWq, tmWoB;
  const __nv_bfloat16 *x0, *wqkv, *woA, *wq, *wk, *wv, *woB;
  __nv_bfloat16* out;
  int m1;
};

__global__ void __launch_bounds__(640, 1) mega(const __grid_constant__ Params p) {
  extern __shared__ __align__(1024) uint8_t sm[];
  PT(63);
  int tid = threadIdx.x, warp = __shfl_sync(~0u, tid >> 5, 0), wg = warp >> 2, wq = warp & 3, lane = tid & 31;
  int bid = blockIdx.x, g = bid >> 2, j = bid & 3;
  uint32_t sb = smem_u32(sm), bars = sb + SM_BAR;
#define REFRESH() do { asm volatile("mov.u32 %0, %%tid.x;" : "=r"(tid)); asm volatile("mov.u32 %0, %%ctaid.x;" : "=r"(bid)); asm volatile("mov.u32 %0, sm;" : "=r"(sb)); warp = __shfl_sync(~0u, tid >> 5, 0); wg = warp >> 2; wq = warp & 3; lane = tid & 31; g = bid >> 2; j = bid & 3; bars = sb + SM_BAR; } while (0)
#define XB(u) (bars + 8 * (B_X + 8 * (u)))
  if (wg == 4) {
    asm volatile("setmaxnreg.dec.sync.aligned.u32 32;");
    if (wq == 0) {
      if (lane == 0) {
#pragma unroll
        for (int i = 0; i < 8; i++) mbar_init(bars + 8 * (B_FULL + i), 1);
        asm volatile("fence.mbarrier_init.release.cluster;" ::: "memory");
        fence_async_smem();
        l2_prefetch((const uint8_t*)p.wqkv + bid * 12288, 12288);
#pragma unroll 1
        for (int n = 0; n < 8; n++) {
          mbar_expect(bars + 8 * (B_FULL + n), 16384);
          tma4(sb + SM_W + n * 16384, &p.tmKV, bars + 8 * (B_FULL + n), 0, 32 * ((4 * j + n) & 15), 2 * j, 1);
        }
      }
      __syncwarp();
    } else if (wq == 3) {
      const uint4 z = make_uint4(0, 0, 0, 0);
      sts128(sb + SM_ZERO + lane * 16, z); sts128(sb + SM_ZERO + 512 + lane * 16, z);
      sts32(sb + SM_ONES + lane * 4, 0x3F803F80u); sts32(sb + SM_ONES + 128 + lane * 4, 0x3F803F80u);
      fence_async_smem();
      __syncwarp();
      reset_piece(0, sb, bid, lane);
      if (lane < 11) reset_piece(0, sb, bid, lane + 32);
      if (lane < 12) str128(&g_fin[0][j][12 * g + lane], z);
      else if (lane < 16) str128(&g_cs[bid * 16 + (lane - 12) * 4], z);
      else if (lane < 24 && bid == 0) str128(&g_cs[2048 + (lane - 16) * 4], z);
      __syncwarp();
    }
    unsigned epoch;
    asm volatile("ld.relaxed.gpu.global.u32 %0, [%1];" : "=r"(epoch) : "l"(g_cnt + 32) : "memory");
    if (wq == 3) {
      reset_wait();
      __syncwarp();
      if (lane == 0) asm volatile("red.release.gpu.global.add.u32 [%0], 1;" ::"l"(g_cnt + 64) : "memory");
      __syncwarp();
    }
    bar_sync(0, 640);
    if (wq == 0) {
      if (lane != 0) return;
#pragma unroll 1
      for (int lyr = 0; lyr < 2; lyr++) {
#pragma unroll 1
        for (int n = lyr ? 0 : 8; n < 40; n++) {
          const int sl = n & 7;
          if (lyr == 0 && n == 8) {
            l2_prefetch((const uint8_t*)p.woA + bid * 4096, 4096);
            l2_prefetch((const uint8_t*)p.wq + bid * 4096, 4096);
            l2_prefetch((const uint8_t*)p.woB + bid * 4096, 4096);
            if (bid < 4) { l2_prefetch((const uint8_t*)p.wk + bid * 4096, 4096); l2_prefetch((const uint8_t*)p.wv + bid * 4096, 4096); }
          }
          mbar_wait(bars + 8 * (B_EMPTY + sl), ((n >> 3) + 1) & 1);
          const uint32_t fb = bars + 8 * (B_FULL + sl), dst = sb + SM_W + sl * 16384;
          mbar_expect(fb, 16384);
          if (n < 16) tma4(dst, &p.tmKV, fb, 0, 32 * ((4 * j + n) & 15), 2 * j, 1);
          else tma3(dst, n < 24 ? &p.tmQ : n < 32 ? &p.tmWoA : &p.tmWq, fb, 0, 64 * ((2 * j + n) & 7), 2 * j);
        }
        poll(g_cnt, (2 * epoch + lyr + 1) * 64);
        PT(28 + lyr * 30);
        fence_async();
        if (lyr == 1 && bid == 0) asm volatile("st.relaxed.gpu.global.u32 [%0], %1;" ::"l"(g_cnt + 32), "r"(epoch + 1) : "memory");
        int es = 0;
#pragma unroll 1
        for (int t = 0; t < 16; t++) {
          const int need = min((STAGE * (t + 1) - 1) >> 14, 7);
          while (es <= need) { mbar_wait(bars + 8 * (B_EMPTY + es), 0); es++; }
          const uint32_t ib = bars + 8 * (B_IMG + t);
          mbar_expect(ib, t == 0 ? STAGE + 256 : STAGE);
          if (t == 0) bulk_g2s(sb + SM_KMAX, g_kmax, 256, ib);
          bulk_g2s(sb + SM_IMG + t * STAGE, g_img + t * STAGE, STAGE, ib);
        }
#pragma unroll 1
        for (int n = 0; n < 8; n++) {
          mbar_wait(bars + 8 * (B_TFREE + ((0xCB976431u >> (4 * n)) & 15)), lyr);
          const uint32_t fb = bars + 8 * (B_FULL + n);
          mbar_expect(fb, 16384);
          tma3(sb + SM_W + n * 16384, &p.tmWoB, fb, 0, 64 * ((2 * j + (ORD_B >> (4 * n))) & 7), 2 * j);
        }
      }
      return;
    }
    int hw = wq - 1;
    if (hw == 2) {
      if (lane == 0) { poll_slow(g_cnt + 64, (2 * epoch + 1) * 128); mbar_arrive(bars + 8 * B_RDY); }
      __syncwarp();
    } else mbar_wait(bars + 8 * B_RDY, 0);
    if (hw < 2 || (j == 2 && g < 4)) {
      const __nv_bfloat16* src;
      int stride, idx;
      if (hw < 2) {
        const int m = g >> 3, col = 128 * j + 16 * (g & 7) + 8 * hw;
        src = m < 3 ? p.wqkv + (m == 2 ? 0 : 512 + 512 * m) + col : p.wq + col;
        stride = m < 3 ? 1536 : 512; idx = j * 512 + 16 * g + 8 * hw;
      } else { src = (g >> 1 ? p.wv : p.wk) + 8 * (g & 1); stride = 16; idx = 2048 + 8 * g; }
      src += lane * stride;
      float s[8];
#pragma unroll
      for (int i = 0; i < 8; i++) s[i] = 0.f;
#pragma unroll 1
      for (int it = 0; it < 4; it++) {
        uint4 v[4];
#pragma unroll
        for (int i = 0; i < 4; i++) { v[i] = ldcg128(src); src += 32 * stride; }
#pragma unroll
        for (int i = 0; i < 4; i++) {
          s[0] += bf_lo(v[i].x); s[1] += bf_hi(v[i].x); s[2] += bf_lo(v[i].y); s[3] += bf_hi(v[i].y);
          s[4] += bf_lo(v[i].z); s[5] += bf_hi(v[i].z); s[6] += bf_lo(v[i].w); s[7] += bf_hi(v[i].w);
        }
      }
#pragma unroll
      for (int o = 16; o; o >>= 1)
#pragma unroll
        for (int i = 0; i < 8; i++) s[i] += __shfl_xor_sync(~0u, s[i], o);
      if (lane == 0) {
        str128(&g_cs[idx], make_uint4(nzf(s[0]), nzf(s[1]), nzf(s[2]), nzf(s[3])));
        str128(&g_cs[idx + 4], make_uint4(nzf(s[4]), nzf(s[5]), nzf(s[6]), nzf(s[7])));
      }
      __syncwarp();
    }
#pragma unroll 1
    for (int half = 0; half < 3; half++) {
      REFRESH(); hw = wq - 1;
      if (hw == 2) {
        const int u = 2 * half + 1;
        mbar_wait(XB(u), 0);
        const uint4* src = &g_ex[u][4 * g][1024 + lane];
        float sh0 = 0.f, sh1 = 0.f, d0 = 0.f, d1 = 0.f, q0 = 0.f, q1 = 0.f;
#pragma unroll 1
        for (int b = 0; b < 2; b++) {
          uint4 v[4];
#pragma unroll 1
          for (int it = 0;; it++) {
#pragma unroll
            for (int i = 0; i < 4; i++) v[i] = ldr128(src + (i >> 1) * 1088 + (i & 1) * 32);
            if (!__any_sync(~0u, pend(v[0]) | pend(v[1]) | pend(v[2]) | pend(v[3]))) break;
            CHK(it);
          }
          if (b == 0) { sh0 = __uint_as_float(v[0].x); sh1 = __uint_as_float(v[0].z); }
#pragma unroll
          for (int i = 0; i < 4; i++) {
            const float a = __uint_as_float(v[i].x) - sh0, c = __uint_as_float(v[i].z) - sh1;
            d0 += a; d1 += c;
            q0 += fmaf(a * 64.f, a, __uint_as_float(v[i].y)); q1 += fmaf(c * 64.f, c, __uint_as_float(v[i].w));
          }
          src += 2 * 1088;
        }
        const float r0 = rsqrtf(fmaxf(q0 - 8.f * d0 * d0, 0.f) * (1.f / 512.f) + 1e-5f), r1 = rsqrtf(fmaxf(q1 - 8.f * d1 * d1, 0.f) * (1.f / 512.f) + 1e-5f);
        const uint32_t a = sb + SM_STAT + ((lane >> 3) * 16 + (lane & 7)) * 8;
        sts32f(a, r0); sts32f(a + 4, -fmaf(d0, 0.125f, sh0) * r0); sts32f(a + 64, r1); sts32f(a + 68, -fmaf(d1, 0.125f, sh1) * r1);
        __syncwarp();
        if (lane == 0) mbar_arrive(XB(u) + 48);
      }
      if (half == 1) continue;
      const int lyr = half >> 1;
      REFRESH(); hw = wq - 1;
      mbar_wait(bars + 8 * B_IMG, lyr);
      if (lyr == 0) {
        if (tid < 544 + 94) reset_piece(1, sb, bid, tid - 544);
        if (tid < 544 + 12) str128(&g_fin[1][j][12 * g + tid - 544], make_uint4(0, 0, 0, 0));
        reset_wait();
        bar_sync(7, 96);
        if (tid == 544) {
          asm volatile("red.release.gpu.global.add.u32 [%0], 1;" ::"l"(g_cnt + 64) : "memory");
          poll_slow(g_cnt + 64, (2 * epoch + 2) * 128);
          mbar_arrive(bars + 8 * B_RDY);
        }
        __syncwarp();
      }
      REFRESH(); hw = wq - 1;
      const int u = 4 * lyr + 2, jj = (j + 1 + hw) & 3;
      mbar_wait(XB(u) + 32, 0);
      const uint4* src = &g_ex[u][4 * g + jj][lane];
#pragma unroll 1
      for (int cb = 0; cb < 4; cb++) {
        uint4 v[4];
#pragma unroll 1
        for (int it = 0;; it++) {
#pragma unroll
          for (int i = 0; i < 4; i++) v[i] = ldr128(src + i * 32);
          if (!__any_sync(~0u, pend(v[0]) | pend(v[1]) | pend(v[2]) | pend(v[3]))) break;
          CHK(it);
          __nanosleep(200);
        }
        const uint32_t ad = (sb + SM_XA + jj * 16384 + blk_addr(0, lane)) ^ (cb << 5);
#pragma unroll
        for (int i = 0; i < 4; i++) stsm4(ad + i * 2048, v[i].x, v[i].y, v[i].z, v[i].w);
        src += 128;
      }
      fence_async_smem();
      __syncwarp();
      if (lane == 0) mbar_arrive(XB(u) + 40);
    }
    return;
  }
  asm volatile("setmaxnreg.inc.sync.aligned.u32 112;");
  PT(15);
  if (lane == 0 && warp >= 1 && warp < 14) {
    const uint32_t ba = bars + 64 * warp;
    if (warp < 6) {
      const uint32_t c = (warp == 1 || warp >= 4) ? 16 : 1;
#pragma unroll
      for (int i = 0; i < 8; i++) mbar_init(ba + 8 * i, c);
    } else if (warp < 13) {
      mbar_init(ba, (warp & 3) == 0 ? 16 : 8);
      mbar_init(ba + 8, 8); mbar_init(ba + 16, 8); mbar_init(ba + 24, 8);
      mbar_init(ba + 32, 16); mbar_init(ba + 40, 3); mbar_init(ba + 48, 1); mbar_init(ba + 56, 4);
    } else mbar_init(ba, 1);
    asm volatile("fence.mbarrier_init.release.cluster;" ::: "memory");
  }
  __syncwarp();

  float acc[32];
  uint4 res[4];
#pragma unroll 1
  for (int half = 0; half < 4; half++) {
    const int lyr = half >> 1;
    REFRESH();
    if (!(half & 1)) {
      float2 cs[8];
      if (lyr == 0) {
        ln_stage(p.x0 + g * 64 * 512, sb, warp, lane, j);
        PT(27);
        fence_async_smem();
        bar_sync(0, 640);
        const uint32_t ad = sb + SM_STG + (wg & 1) * 8192 + blk_addr(wq, lane);
#pragma unroll
        for (int q = 0; q < 4; q++) ldsm4(ad ^ (q << 5), (uint32_t*)&res[q]);
      } else {
        load_cs<4>(cs, &g_cs[j * 512 + wg * 64 + 2 * (lane & 3)]);
      }
      PT(0 + lyr * 30);
      {
#pragma unroll
        for (int i = 0; i < 32; i++) acc[i] = 0.f;
        const uint64_t a0 = desc_sw(sb + SM_XA), b0 = desc_sw(sb + SM_W + wg * 4096);
        fence_regs<32>(acc);
#pragma unroll 1
        for (int s = 0; s < 16; s++) {
          const int kb = (4 * j + s) & 15;
          const uint64_t a = a0 + (kb >> 1) * 512 + (kb & 1) * 4, b = b0 + (s & 7) * 1024;
          if (lyr == 1 && (s & 3) == 0) mbar_wait(XB(3) + 2 * s, 0);
          mbar_wait(bars + 8 * (B_FULL + (s & 7)), s >> 3);
          wg_fence();
          ss_n64<0, 1>(acc, a, b); ss_n64<0, 1>(acc, a + 2, b + 128);
          wg_commit();
          wg_wait<1>();
          if (s > 0 && lane == 0) mbar_arrive(bars + 8 * (B_EMPTY + ((s - 1) & 7)));
        }
        wg_wait<0>();
        fence_regs<32>(acc);
        if (lane == 0) mbar_arrive(bars + 8 * (B_EMPTY + 7));
      }
      PT(1 + lyr * 30);
      if (lyr == 1) { mbar_wait(XB(3) + 48, 0); ln_fold<4>(acc, cs, sb, wq, lane); }
      if (wg < 2) {
#pragma unroll
        for (int i = 0; i < 32; i++) acc[i] = phi(acc[i]);
      }
      {
        const uint32_t ad = sb + SM_STG + wg * 8192 + blk_addr(wq, lane);
#pragma unroll
        for (int q = 0; q < 4; q++)
          stsm4(ad ^ (q << 5), pack_bf(acc[8 * q], acc[8 * q + 1]), pack_bf(acc[8 * q + 2], acc[8 * q + 3]),
                pack_bf(acc[8 * q + 4], acc[8 * q + 5]), pack_bf(acc[8 * q + 6], acc[8 * q + 7]));
      }
      fence_async_smem();
      if (wg < 2) {
        PT(2 + lyr * 30);
        bar_sync(2 + wg, 256);
        float z[4] = {0.f, 0.f, 0.f, 0.f};
#pragma unroll
        for (int i = 0; i < 32; i++) acc[i] = 0.f;
        const uint64_t a = desc_sw(sb + SM_STG + wg * 8192), b = desc_sw(sb + SM_STG + (2 + wg) * 8192), o = desc_ns(sb + SM_ONES, 128, 128);
        fence_regs<32>(acc); fence_regs<4>(z);
        wg_fence();
#pragma unroll
        for (int kk = 0; kk < 4; kk++) { ss_n64<1, 1>(acc, a + kk * 128, b + kk * 128); ss_n8<1, 0>(z, a + kk * 128, o); }
        wg_commit();
        wg_wait<0>();
        fence_regs<32>(acc); fence_regs<4>(z);
        PT(3 + lyr * 30);
        mbar_wait(bars + 8 * B_RDY, lyr);
        {
          float r[8];
#pragma unroll
          for (int i = 0; i < 8; i++) r[i] = wq == 0 ? acc[i] : wq == 1 ? acc[8 + i] : wq == 2 ? acc[16 + i] : acc[24 + i];
          const bool od = lane & 1;
          const float e0 = __shfl_xor_sync(~0u, od ? r[0] : r[2], 1), e1 = __shfl_xor_sync(~0u, od ? r[1] : r[3], 1);
          const float e2 = __shfl_xor_sync(~0u, od ? r[4] : r[6], 1), e3 = __shfl_xor_sync(~0u, od ? r[5] : r[7], 1);
          const float z0 = __shfl_sync(~0u, z[0], lane & 24), z2 = __shfl_sync(~0u, z[2], lane & 24);
          const float z1 = __shfl_sync(~0u, z[0], (lane & 24) + 4), z3 = __shfl_sync(~0u, z[2], (lane & 24) + 4);
          uint4* dst = &g_part[lyr][j][4 * warp + (lane >> 3)][g * 18];
          uint4* d2 = dst + (((lane >> 2) & 1) + 2 * od) * 4 + ((lane >> 1) & 1);
          str128(d2, od ? make_uint4(nzf(e0), nzf(e1), nzf(r[2]), nzf(r[3])) : make_uint4(nzf(r[0]), nzf(r[1]), nzf(e0), nzf(e1)));
          str128(d2 + 2, od ? make_uint4(nzf(e2), nzf(e3), nzf(r[6]), nzf(r[7])) : make_uint4(nzf(r[4]), nzf(r[5]), nzf(e2), nzf(e3)));
          if ((lane & 7) < 2) str128(dst + 16 + (lane & 1), make_uint4(nzf(z0), nzf(z1), nzf(z2), nzf(z3)));
        }
        PT(4 + lyr * 30);
        bar_arrive(5, 512);
        if (warp < 5) {
          const uint4* src = &g_part[lyr][j][g][(lane >> 2) * 72 + (warp < 4 ? warp * 4 + (lane & 3) : 16)];
          uint4 v[4];
#pragma unroll
          for (int i = 0; i < 4; i++) v[i] = ldr128(src + i * 18);
#pragma unroll 1
          for (int it = 0;; it++) {
            bool any = false;
#pragma unroll
            for (int i = 0; i < 4; i++)
              if (pend(v[i])) { v[i] = ldr128(src + i * 18); any = true; }
            if (!__any_sync(~0u, any)) break;
            CHK(it);
          }
#define F(x) __uint_as_float(x)
          float s0 = (F(v[0].x) + F(v[1].x)) + (F(v[2].x) + F(v[3].x)), s1 = (F(v[0].y) + F(v[1].y)) + (F(v[2].y) + F(v[3].y));
          float s2 = (F(v[0].z) + F(v[1].z)) + (F(v[2].z) + F(v[3].z)), s3 = (F(v[0].w) + F(v[1].w)) + (F(v[2].w) + F(v[3].w));
          __syncwarp();
#pragma unroll
          for (int o = 4; o < 32; o <<= 1) {
            s0 += __shfl_xor_sync(~0u, s0, o); s1 += __shfl_xor_sync(~0u, s1, o);
            s2 += __shfl_xor_sync(~0u, s2, o); s3 += __shfl_xor_sync(~0u, s3, o);
          }
          uint4* fin = &g_fin[lyr][j][(g >> 2) * 48 + 2 * (g & 3)];
          if (warp < 4) {
            const uint32_t w0 = nz(pack_bf(s0, s1)), w1 = nz(pack_bf(s2, s3));
            const uint32_t w2 = __shfl_xor_sync(~0u, w0, 1), w3 = __shfl_xor_sync(~0u, w1, 1);
            if (lane == 0 || lane == 2) str128(fin + lane * 8 + (warp & 1) + (warp >> 1) * 8, make_uint4(w0, w1, w2, w3));
          } else if (lane < 4) {
            const float zz = lane == 0 ? s0 : lane == 1 ? s1 : lane == 2 ? s2 : s3;
            const uint32_t w = nz(pack_bf(zz, zz));
            str128(fin + 32 + (lane & 1) + (lane >> 1) * 8, make_uint4(w, w, w, w));
          }
        }
        PT(5 + lyr * 30);
        bar_sync(4, 256);
        {
          const uint4* src = &g_fin[lyr][j][tid];
          uint4 v0 = ldr128(src), v1 = make_uint4(1, 1, 1, 1);
          if (tid < 128) v1 = ldr128(src + 256);
#pragma unroll 1
          for (int it = 0;; it++) {
            bool any = false;
            if (pend(v0)) { v0 = ldr128(src); any = true; }
            if (pend(v1)) { v1 = ldr128(src + 256); any = true; }
            if (!__any_sync(~0u, any)) break;
            CHK(it);
          }
          sts128(sb + SM_STG + tid * 16, v0);
          if (tid < 128) sts128(sb + SM_STG + 4096 + tid * 16, v1);
          fence_async_smem();
        }
        PT(6 + lyr * 30);
        bar_sync(1, 512);
      } else {
        bar_arrive(wg, 256);
        if (lyr == 1) load_cs<4>(cs, &g_cs[j * 512 + 128 + wg * 64 + 2 * (lane & 3)]);
        bar_sync(5, 512);
        gemm8(acc, sb, bars, 0, wg - 2, lane, j, ORD_A, 0, ~0u);
        PT(7 + lyr * 30);
        if (lyr == 1) ln_fold<4>(acc, cs, sb, wq, lane);
        uint32_t pq[16];
#pragma unroll
        for (int i = 0; i < 16; i++) pq[i] = pack_bf(phi(acc[2 * i]), phi(acc[2 * i + 1]));
        float o[48];
#pragma unroll
        for (int i = 0; i < 48; i++) o[i] = 0.f;
        const uint64_t b = desc_ns(sb + SM_STG + (wg - 2) * 4 * 768, 256, 128);
        fence_regs<48>(o);
        PT(8 + lyr * 30);
        bar_sync(1, 512);
        wg_fence();
#pragma unroll
        for (int q = 0; q < 4; q++) pv_n24(o + 12 * q, pq + 4 * q, b + q * 48);
        wg_commit();
        wg_wait<0>();
        fence_regs<48>(o);
        uint4* dst = &g_ex[2 * half][bid][(wg - 2) * 512 + wq * 32 + lane];
        const uint32_t ad = sb + SM_XA + (2 * j + wg - 2) * 8192 + blk_addr(wq, lane);
#pragma unroll
        for (int q = 0; q < 4; q++) {
          const float* oo = o + 12 * q;
          const float i0 = rcp(oo[8] + 1e-6f), i1 = rcp(oo[10] + 1e-6f);
          const uint4 w = make_uint4(nz(pack_bf(oo[0] * i0, oo[1] * i0)), nz(pack_bf(oo[2] * i1, oo[3] * i1)), nz(pack_bf(oo[4] * i0, oo[5] * i0)), nz(pack_bf(oo[6] * i1, oo[7] * i1)));
          str128(dst + q * 128, w);
          stsm4(ad ^ (q << 5), w.x, w.y, w.z, w.w);
        }
        fence_async_smem();
        __syncwarp();
        if (lane == 0) mbar_arrive(XB(2 * half));
        PT(9 + lyr * 30);
#pragma unroll
        for (int q = 0; q < 4; q++) res[q] = make_uint4(0, 0, 0, 0);
      }
    } else {
      const uint32_t xb = XB(2 * half - 1);
      if (wg < 2) {
        float2 cs[8];
        load_cs<4>(cs, &g_cs[j * 512 + 384 + wg * 64 + 2 * (lane & 3)]);
        gemm8(acc, sb, bars, 0, wg, lane, j, ORD_A, xb, j < 2 ? KVT : 0xF3F2F1F0u);
        PT(16 + lyr * 30);
        mbar_wait(xb + 48, 0);
        ln_fold<4>(acc, cs, sb, wq, lane);
        bar_sync(4, 256);
        const uint32_t ad = sb + SM_XA + (2 * j + wg) * 8192 + blk_addr(wq, lane);
#pragma unroll
        for (int q = 0; q < 4; q++)
          stsm4(ad ^ (q << 5), pack_bf(acc[8 * q], acc[8 * q + 1]), pack_bf(acc[8 * q + 2], acc[8 * q + 3]),
                pack_bf(acc[8 * q + 4], acc[8 * q + 5]), pack_bf(acc[8 * q + 6], acc[8 * q + 7]));
      } else if (wg == 2 && j < 2) {
        float2 cs[2];
        load_cs<1>(cs, &g_cs[2048 + 16 * j + 2 * (lane & 3)]);
        float d[8];
#pragma unroll
        for (int i = 0; i < 8; i++) d[i] = 0.f;
        const uint64_t a = desc_sw(sb + SM_XA), b = desc_ns(sb + SM_STG + 16384, 8192, 128);
        fence_regs<8>(d);
        mbar_wait(xb, 0); mbar_wait(xb + 8, 0); mbar_wait(xb + 16, 0); mbar_wait(xb + 24, 0);
        wg_fence();
#pragma unroll
        for (int ks = 0; ks < 32; ks++) ss_n16<0, 1>(d, a + (ks >> 2) * 512 + (ks & 3) * 2, b + ks * 16);
        wg_commit();
        wg_wait<0>();
        fence_regs<8>(d);
        PT(17 + lyr * 30);
        mbar_wait(xb + 48, 0);
        ln_fold<1>(d, cs, sb, wq, lane);
        const uint32_t st = sb + SM_STG;
        const int r = 16 * wq + (lane >> 2), c = lane & 3;
        sts32(st + r * 48 + c * 4, pack_bf(d[0], d[1])); sts32(st + (r + 8) * 48 + c * 4, pack_bf(d[2], d[3]));
        sts32(st + r * 48 + 16 + c * 4, pack_bf(d[4], d[5])); sts32(st + (r + 8) * 48 + 16 + c * 4, pack_bf(d[6], d[7]));
        bar_sync(6, 128);
        const int tok = 32 * (wq >> 1) + lane, ch = 2 * g + (wq >> 1), oc = wq & 1;
        uint4 v0 = lds128(st + tok * 48 + oc * 16);
        uint8_t* ip = g_img + (lane >> 1) * STAGE + ((lane & 1) * 64 + ch) * 16 + oc * 2048;
        if (j == 1) {
          const uint32_t sg = ((MUMASK >> ((ch >> 3) & 7)) & 1) ? 0x80008000u : 0u;
          v0.x ^= sg; v0.y ^= sg; v0.z ^= sg; v0.w ^= sg;
          *(uint4*)(ip + 4096) = v0;
          if (oc == 0) *(uint4*)(ip + 8192) = make_uint4(0x3F80u | (sg & 0x8000u), 0, 0, 0);
        } else {
          const uint32_t u[4] = {v0.x, v0.y, v0.z, v0.w};
          float dl[8];
#pragma unroll
          for (int i = 0; i < 8; i++) {
            const float kx = (i & 1) ? bf_hi(u[i >> 1]) : bf_lo(u[i >> 1]);
            uint32_t e = __reduce_max_sync(~0u, __float_as_uint(kx) & 0x7fffffffu) >> 23;
            e = min(max(e, 112u), 200u);
            const float M = __uint_as_float(((e + 14) << 23) | 0x400000u);
            const float kq = __fsub_rn(__fadd_rn(kx, M), M);
            float pv = __shfl_up_sync(~0u, kq, 1);
            if (lane == 0) pv = 0.f;
            dl[i] = kq - pv;
          }
          *(uint4*)ip = make_uint4(pack_hf(dl[0], dl[1]), pack_hf(dl[2], dl[3]), pack_hf(dl[4], dl[5]), pack_hf(dl[6], dl[7]));
          *(uint4*)(g_kp + (g * 64 + tok) * 16 + oc * 8) = v0;
          if (oc == 0) {
            const uint4 v1 = lds128(st + tok * 48 + 16);
            const uint32_t w[8] = {v0.x, v0.y, v0.z, v0.w, v1.x, v1.y, v1.z, v1.w};
            float nn = 0.f;
#pragma unroll
            for (int i = 0; i < 8; i++) nn = fmaf(bf_lo(w[i]), bf_lo(w[i]), fmaf(bf_hi(w[i]), bf_hi(w[i]), nn));
            uint32_t nm = __reduce_max_sync(~0u, __float_as_uint(nn));
            if (nm >= 0x4D800000u) nm = 0x7f800000u;
            if (lane == 0) g_kmax[ch] = sqrtf(__uint_as_float(nm));
          }
        }
        PT(18 + lyr * 30);
        __syncwarp();
        if (lane == 0) mbar_arrive(xb + 56);
        bar_sync(6, 128);
        if (tid == 256) asm volatile("red.release.gpu.global.add.u32 [%0], 1;" ::"l"(g_cnt) : "memory");
        PT(19 + lyr * 30);
        __syncwarp();
      }
      bar_sync(1, 512);
      PT(20 + lyr * 30);
      REFRESH();
#pragma unroll 1
      for (int pass = 0; pass < 2; pass++) {
        attn_pass(pass, sb, lyr, p.m1);
        if (pass == 0) PT(21 + lyr * 30);
        else PT(22 + lyr * 30);
      }
      REFRESH();
#pragma unroll
      for (int q = 0; q < 4; q++) res[q] = wg < 2 ? ldr128(&g_ex[2 * half - 1][bid][wg * 512 + q * 128 + wq * 32 + lane]) : make_uint4(0, 0, 0, 0);
    }
    REFRESH();
    const int pb = lyr * 30 + (half & 1) * 13;
    if (wg < 2) {
      gemm8(acc, sb, bars, 1, wg, lane, j, (half & 1) ? ORD_B : ORD_A, XB(2 * half), (half & 1) ? 0x3210FF54u : 0xF3F2F1F0u);
      PT(10 + pb);
      const uint32_t ad = sb + SM_XA + (2 * j + wg) * 8192 + blk_addr(wq, lane);
      uint4* dst = &g_ex[half < 3 ? 2 * half + 1 : 0][bid][wg * 512 + wq * 32 + lane];
      const uint32_t lo = half < 3;
#pragma unroll
      for (int q = 0; q < 4; q++) {
        res[q].x = max(add_bf2(pack_bf(acc[8 * q], acc[8 * q + 1]), res[q].x), lo); res[q].y = max(add_bf2(pack_bf(acc[8 * q + 2], acc[8 * q + 3]), res[q].y), lo);
        res[q].z = max(add_bf2(pack_bf(acc[8 * q + 4], acc[8 * q + 5]), res[q].z), lo); res[q].w = max(add_bf2(pack_bf(acc[8 * q + 6], acc[8 * q + 7]), res[q].w), lo);
        if (half < 3) str128(dst + q * 128, res[q]);
      }
      bar_sync(1, 512);
#pragma unroll
      for (int q = 0; q < 4; q++) stsm4(ad ^ (q << 5), res[q].x, res[q].y, res[q].z, res[q].w);
      if (half < 3) {
        fence_async_smem();
        __syncwarp();
        if (lane == 0) mbar_arrive(XB(2 * half + 1));
        PT(11 + pb);
        float m0 = 0.f, m1 = 0.f, q0 = 0.f, q1 = 0.f;
#pragma unroll
        for (int q = 0; q < 4; q++) {
          m0 += (bf_lo(res[q].x) + bf_hi(res[q].x)) + (bf_lo(res[q].z) + bf_hi(res[q].z));
          m1 += (bf_lo(res[q].y) + bf_hi(res[q].y)) + (bf_lo(res[q].w) + bf_hi(res[q].w));
        }
        m0 *= 0.0625f; m1 *= 0.0625f;
#pragma unroll
        for (int q = 0; q < 4; q++) {
          float a = bf_lo(res[q].x) - m0, b = bf_hi(res[q].x) - m0, c = bf_lo(res[q].z) - m0, d = bf_hi(res[q].z) - m0;
          q0 += (a * a + b * b) + (c * c + d * d);
          a = bf_lo(res[q].y) - m1; b = bf_hi(res[q].y) - m1; c = bf_lo(res[q].w) - m1; d = bf_hi(res[q].w) - m1;
          q1 += (a * a + b * b) + (c * c + d * d);
        }
#pragma unroll
        for (int o = 1; o < 4; o <<= 1) {
          const float a0 = __shfl_xor_sync(~0u, m0, o), a1 = __shfl_xor_sync(~0u, m1, o), b0 = __shfl_xor_sync(~0u, q0, o), b1 = __shfl_xor_sync(~0u, q1, o);
          q0 = fmaf((m0 - a0) * (8.f * o), m0 - a0, q0 + b0); q1 = fmaf((m1 - a1) * (8.f * o), m1 - a1, q1 + b1);
          m0 = 0.5f * (m0 + a0); m1 = 0.5f * (m1 + a1);
        }
        if ((lane & 3) == 0) str128(&g_ex[2 * half + 1][bid][1024 + warp * 8 + (lane >> 2)], make_uint4(nzf(m0), nzf(q0), nzf(m1), nzf(q1)));
      } else {
        __syncwarp();
        const uint32_t st = sb + SM_XA + (2 * j + wg) * 8192 + wq * 2048;
        __nv_bfloat16* op = p.out + (g * 64 + 16 * wq + (lane >> 3)) * 512 + 128 * j + 64 * wg + (lane & 7) * 8;
#pragma unroll
        for (int i = 0; i < 4; i++) {
          const int row = i * 4 + (lane >> 3);
          *(uint4*)(op + i * 4 * 512) = lds128(st + row * 128 + (((lane & 7) ^ (row & 7)) << 4));
        }
      }
      PT(12 + pb);
    } else {
      gather(2 * half, sb, g, j, warp - 8, lane, half & 1);
      PT(10 + pb);
      if (half == 3) { bar_arrive(1, 512); break; }
      if (!(half & 1) && j < 2) {
        const __nv_bfloat16* w = j == 0 ? p.wk : p.wv;
#pragma unroll
        for (int i = 0; i < 4; i++) {
          const int id = (tid - 256) + i * 256;
          uint4 v = *(const uint4*)(w + id * 8);
          sts128(sb + SM_STG + 16384 + (id & 1) * 8192 + (id >> 1) * 16, v);
        }
        fence_async_smem();
      }
      bar_sync(1, 512);
      PT(11 + pb);
      gather(2 * half + 1, sb, g, j, warp - 8, lane, false);
      PT(12 + pb);
    }
  }
}

typedef CUresult (*EncFn)(CUtensorMap*, CUtensorMapDataType, cuuint32_t, void*, const cuuint64_t*, const cuuint64_t*, const cuuint32_t*, const cuuint32_t*,
                          CUtensorMapInterleave, CUtensorMapSwizzle, CUtensorMapL2promotion, CUtensorMapFloatOOBfill);

static void enc_map(EncFn enc, CUtensorMap* m, const void* ptr, int rank, const cuuint64_t* gd, const cuuint64_t* gs, const cuuint32_t* bd) {
  cuuint32_t es[4] = {1, 1, 1, 1};
  enc(m, CU_TENSOR_MAP_DATA_TYPE_BFLOAT16, rank, (void*)ptr, gd, gs, bd, es, CU_TENSOR_MAP_INTERLEAVE_NONE, CU_TENSOR_MAP_SWIZZLE_128B,
      CU_TENSOR_MAP_L2_PROMOTION_L2_128B, CU_TENSOR_MAP_FLOAT_OOB_FILL_NONE);
}

extern "C" void kernel_launch(void* const* d_in, const int* in_sizes, int n_in, void* d_out, int out_size) {
  static EncFn enc = nullptr;
  if (!enc) {
    cudaDriverEntryPointQueryResult qr;
    cudaGetDriverEntryPoint("cuTensorMapEncodeTiled", (void**)&enc, cudaEnableDefault, &qr);
    cudaFuncSetAttribute(mega, cudaFuncAttributeMaxDynamicSharedMemorySize, SM_TOTAL);
  }
  Params p;
  {
    cuuint64_t gd[4] = {64, 512, 8, 3}, gs[3] = {3072, 128, 1024};
    cuuint32_t bd[4] = {64, 32, 2, 2};
    enc_map(enc, &p.tmKV, d_in[1], 4, gd, gs, bd);
  }
  {
    cuuint64_t gd[3] = {64, 512, 24}, gs[2] = {3072, 128};
    cuuint32_t bd[3] = {64, 64, 2};
    enc_map(enc, &p.tmQ, d_in[1], 3, gd, gs, bd);
  }
  {
    cuuint64_t gd[3] = {64, 512, 8}, gs[2] = {1024, 128};
    cuuint32_t bd[3] = {64, 64, 2};
    enc_map(enc, &p.tmWoA, d_in[2], 3, gd, gs, bd);
    enc_map(enc, &p.tmWq, d_in[4], 3, gd, gs, bd);
    enc_map(enc, &p.tmWoB, d_in[7], 3, gd, gs, bd);
  }
  p.x0 = (const __nv_bfloat16*)d_in[0];
  p.wqkv = (const __nv_bfloat16*)d_in[1];
  p.woA = (const __nv_bfloat16*)d_in[2];
  p.wq = (const __nv_bfloat16*)d_in[4];
  p.wk = (const __nv_bfloat16*)d_in[5];
  p.wv = (const __nv_bfloat16*)d_in[6];
  p.woB = (const __nv_bfloat16*)d_in[7];
  p.out = (__nv_bfloat16*)d_out; p.m1 = -1;
  mega<<<128, 640, SM_TOTAL, cudaStreamPerThread>>>(p);
}
```
